```python
import torch

def _softmax(x, axis=-1):
    return torch.softmax(x, dim=axis)
def _gelu(x):
    return torch.nn.functional.gelu(x, approximate="tanh")
def _silu(x):
    return torch.nn.functional.silu(x)
def _sigmoid(x):
    return torch.sigmoid(x)
def _layernorm(x, axis=-1, eps=1e-5):
    m = x.mean(dim=axis, keepdim=True)
    v = x.var(dim=axis, keepdim=True, unbiased=False)
    return (x - m) / torch.sqrt(v + eps)
def _scatter_add(tgt, idx, src, axis=0):
    return tgt.clone().index_add_(axis, idx, src)
def _segment_sum(src, seg, n):
    out = torch.zeros((n,) + src.shape[1:], dtype=src.dtype)
    return out.index_add_(0, seg, src)
def _pad(x, pw):
    flat = tuple(v for pair in reversed(pw) for v in pair)
    return torch.nn.functional.pad(x, flat)

kernel_name = 'concat_heads__mha_block__linear_attn_block__prompt'

def setup_inputs():

    _w = (lambda a: (lambda t: t.to(torch.bfloat16) if t.is_floating_point() else t)(torch.as_tensor(a)))
    def _A_setup():
        B, S, D, H = 1, 2048, 1024, 32
        return {
            "x": _w((lambda *s: torch.randn(*s, dtype=torch.bfloat16) * 0.2)(B, S, D)),
            "wqkv": _w((lambda *s: torch.randn(*s, dtype=torch.bfloat16) * 0.2)(D, 3 * D)),
            "wo": _w((lambda *s: torch.randn(*s, dtype=torch.bfloat16) * 0.05)(D, D)),
        }
    _A_in = _A_setup()

    def _B_setup():
        B, S, D = 1, 2048, 1024
        return {
            "x": _w((lambda *s: torch.randn(*s, dtype=torch.bfloat16) * 0.05)(B, S, D)),
            "wqkv": _w((lambda *s: torch.randn(*s, dtype=torch.bfloat16) * 1.6)(D, 3 * D)),
            "wo": _w((lambda *s: torch.randn(*s, dtype=torch.bfloat16) * 0.1)(D, D)),
        }
    _B_in = _B_setup()

    return {
        "A_x": _A_in["x"],
        "A_wqkv": _A_in["wqkv"],
        "A_wo": _A_in["wo"],
        "B_x": _B_in["x"],
        "B_wqkv": _B_in["wqkv"],
        "B_wo": _B_in["wo"],
    }

def reference(A_x, A_wqkv, A_wo, B_x, B_wqkv, B_wo):
    def _A_ref(x, wqkv, wo):
        B, S, D = x.shape
        H = 32
        Dh = D // H
        qkv = (lambda x, *d: x.permute(*d))((x @ wqkv).reshape(B, S, 3, H, Dh), 2, 0, 3, 1, 4)
        q, k, v = qkv[0], qkv[1], qkv[2]
        scores = torch.einsum("bhqd,bhkd->bhqk", q, k) * (Dh ** -0.5)
        p = _softmax(scores, axis=-1)
        o = torch.einsum("bhqk,bhkd->bhqd", p, v)
        return (lambda x, *d: x.permute(*d))(o, 0, 2, 1, 3).reshape(B, S, D) @ wo

    def _B_ref(x, wqkv, wo):
        B, S, D = x.shape
        H = 32; Dh = D // H
        qkv = (lambda x, *d: x.permute(*d))((x @ wqkv).reshape(B, S, 3, H, Dh), 2, 0, 3, 1, 4)
        q, k, v = qkv[0], qkv[1], qkv[2]
        phi = lambda t: torch.where(t > 0, t + 1, torch.exp(t)) + 1e-6
        pq, pk = phi(q), phi(k)
        kv = torch.einsum("bhsd,bhse->bhde", pk, v)
        z = torch.einsum("bhsd->bhd", pk)
        num = torch.einsum("bhqd,bhde->bhqe", pq, kv)
        den = torch.einsum("bhqd,bhd->bhq", pq, z)[..., None] + 1e-6
        o = num / den
        return (lambda x, *d: x.permute(*d))(o, 0, 2, 1, 3).reshape(B, S, D) @ wo

    a = _A_ref(A_x, A_wqkv, A_wo)
    b = _B_ref(B_x, B_wqkv, B_wo)
    return torch.concatenate([a, b], axis=-1)
```

```cpp
#include <cuda_runtime.h>
#include <cuda_bf16.h>
#include <cuda.h>
#include <stdint.h>

namespace {

constexpr int SEQ = 2048;
constexpr int DM = 1024;

constexpr uint32_t G_SLOT = 32768;
constexpr uint32_t G_STAGES = 4;
constexpr uint32_t OFF_STG = G_SLOT * G_STAGES;
constexpr uint32_t STG = 8192;
constexpr uint32_t OFF_A = OFF_STG + 4 * STG;
constexpr uint32_t A_SLOT = 16384;
constexpr uint32_t A_STAGES = 3;
constexpr uint32_t OFF_Q = OFF_A + A_SLOT * A_STAGES;
constexpr uint32_t OFF_KVZ = OFF_Q + 8192;
constexpr uint32_t OFF_BAR = OFF_KVZ + 10240;
constexpr uint32_t SMEM_BYTES = OFF_BAR + 512;

constexpr uint32_t B_GFULL = 0, B_GEMPTY = 4, B_KFULL = 8, B_KEMPTY = 11, B_QFULL = 14, B_QEMPTY = 15, B_KVZ = 16,
                   B_DONE = 17, B_GSIG = 18  , B_ASIG = 24  , B_VFULL = 28, B_VEMPTY = 31,
                   B_KVLD = 34;

constexpr int F_QKVA = 0, F_KVB = 16, F_OA = 32  , F_OB = 48, F_OA2 = 64  ;
__device__ __nv_bfloat16 g_qkvA[3 * 32 * SEQ * 32];
__device__ __nv_bfloat16 g_oA[SEQ * DM];
__device__ __nv_bfloat16 g_oB[SEQ * DM];
__device__ float g_kv[2][32 * 32 * 32];
__device__ float g_z[2][32 * 32];
__device__ unsigned g_flags[80 * 32];
__device__ unsigned g_epoch[128];

struct Params {
  CUtensorMap xA, xB, wA, wB, woA, woB, oA, oB, qkv, out;
};

__device__ __forceinline__ void wgmma_n128_ss_tb(float (&d)[64], uint64_t descA, uint64_t descB, int scaleD) {
  asm volatile("{\n.reg .pred p;\nsetp.ne.b32 p, %66, 0;\n"
    "wgmma.mma_async.sync.aligned.m64n128k16.f32.bf16.bf16 "
    "{%0, %1, %2, %3, %4, %5, %6, %7, %8, %9, %10, %11, %12, %13, %14, %15, "
    "%16, %17, %18, %19, %20, %21, %22, %23, %24, %25, %26, %27, %28, %29, %30, %31, "
    "%32, %33, %34, %35, %36, %37, %38, %39, %40, %41, %42, %43, %44, %45, %46, %47, "
    "%48, %49, %50, %51, %52, %53, %54, %55, %56, %57, %58, %59, %60, %61, %62, %63}, "
    "%64, %65, p, 1, 1, 0, 1;\n}\n"
    : "+f"(d[0]), "+f"(d[1]), "+f"(d[2]), "+f"(d[3]), "+f"(d[4]), "+f"(d[5]), "+f"(d[6]), "+f"(d[7]),
      "+f"(d[8]), "+f"(d[9]), "+f"(d[10]), "+f"(d[11]), "+f"(d[12]), "+f"(d[13]), "+f"(d[14]), "+f"(d[15]),
      "+f"(d[16]), "+f"(d[17]), "+f"(d[18]), "+f"(d[19]), "+f"(d[20]), "+f"(d[21]), "+f"(d[22]), "+f"(d[23]),
      "+f"(d[24]), "+f"(d[25]), "+f"(d[26]), "+f"(d[27]), "+f"(d[28]), "+f"(d[29]), "+f"(d[30]), "+f"(d[31]),
      "+f"(d[32]), "+f"(d[33]), "+f"(d[34]), "+f"(d[35]), "+f"(d[36]), "+f"(d[37]), "+f"(d[38]), "+f"(d[39]),
      "+f"(d[40]), "+f"(d[41]), "+f"(d[42]), "+f"(d[43]), "+f"(d[44]), "+f"(d[45]), "+f"(d[46]), "+f"(d[47]),
      "+f"(d[48]), "+f"(d[49]), "+f"(d[50]), "+f"(d[51]), "+f"(d[52]), "+f"(d[53]), "+f"(d[54]), "+f"(d[55]),
      "+f"(d[56]), "+f"(d[57]), "+f"(d[58]), "+f"(d[59]), "+f"(d[60]), "+f"(d[61]), "+f"(d[62]), "+f"(d[63])
    : "l"(descA), "l"(descB), "r"(scaleD));
}
__device__ __forceinline__ void wgmma_n72_ss_ta_tb(float (&d)[36], uint64_t descA, uint64_t descB, int scaleD) {
  asm volatile("{\n.reg .pred p;\nsetp.ne.b32 p, %38, 0;\n"
    "wgmma.mma_async.sync.aligned.m64n72k16.f32.bf16.bf16 "
    "{%0, %1, %2, %3, %4, %5, %6, %7, %8, %9, %10, %11, %12, %13, %14, %15, "
    "%16, %17, %18, %19, %20, %21, %22, %23, %24, %25, %26, %27, %28, %29, %30, %31, "
    "%32, %33, %34, %35}, "
    "%36, %37, p, 1, 1, 1, 1;\n}\n"
    : "+f"(d[0]), "+f"(d[1]), "+f"(d[2]), "+f"(d[3]), "+f"(d[4]), "+f"(d[5]), "+f"(d[6]), "+f"(d[7]),
      "+f"(d[8]), "+f"(d[9]), "+f"(d[10]), "+f"(d[11]), "+f"(d[12]), "+f"(d[13]), "+f"(d[14]), "+f"(d[15]),
      "+f"(d[16]), "+f"(d[17]), "+f"(d[18]), "+f"(d[19]), "+f"(d[20]), "+f"(d[21]), "+f"(d[22]), "+f"(d[23]),
      "+f"(d[24]), "+f"(d[25]), "+f"(d[26]), "+f"(d[27]), "+f"(d[28]), "+f"(d[29]), "+f"(d[30]), "+f"(d[31]),
      "+f"(d[32]), "+f"(d[33]), "+f"(d[34]), "+f"(d[35])
    : "l"(descA), "l"(descB), "r"(scaleD));
}
__device__ __forceinline__ void wgmma_n40_ss(float (&d)[20], uint64_t descA, uint64_t descB, int scaleD) {
  asm volatile("{\n.reg .pred p;\nsetp.ne.b32 p, %22, 0;\n"
    "wgmma.mma_async.sync.aligned.m64n40k16.f32.bf16.bf16 "
    "{%0, %1, %2, %3, %4, %5, %6, %7, %8, %9, %10, %11, %12, %13, %14, %15, "
    "%16, %17, %18, %19}, "
    "%20, %21, p, 1, 1, 0, 0;\n}\n"
    : "+f"(d[0]), "+f"(d[1]), "+f"(d[2]), "+f"(d[3]), "+f"(d[4]), "+f"(d[5]), "+f"(d[6]), "+f"(d[7]),
      "+f"(d[8]), "+f"(d[9]), "+f"(d[10]), "+f"(d[11]), "+f"(d[12]), "+f"(d[13]), "+f"(d[14]), "+f"(d[15]),
      "+f"(d[16]), "+f"(d[17]), "+f"(d[18]), "+f"(d[19])
    : "l"(descA), "l"(descB), "r"(scaleD));
}
__device__ __forceinline__ void wgmma_n64_rs(float (&d)[32], uint32_t a0, uint32_t a1, uint32_t a2, uint32_t a3, uint64_t descB, int scaleD) {
  asm volatile("{\n.reg .pred p;\nsetp.ne.b32 p, %37, 0;\n"
    "wgmma.mma_async.sync.aligned.m64n64k16.f32.bf16.bf16 "
    "{%0, %1, %2, %3, %4, %5, %6, %7, %8, %9, %10, %11, %12, %13, %14, %15, "
    "%16, %17, %18, %19, %20, %21, %22, %23, %24, %25, %26, %27, %28, %29, %30, %31}, "
    "{%32, %33, %34, %35}, %36, p, 1, 1, 0;\n}\n"
    : "+f"(d[0]), "+f"(d[1]), "+f"(d[2]), "+f"(d[3]), "+f"(d[4]), "+f"(d[5]), "+f"(d[6]), "+f"(d[7]),
      "+f"(d[8]), "+f"(d[9]), "+f"(d[10]), "+f"(d[11]), "+f"(d[12]), "+f"(d[13]), "+f"(d[14]), "+f"(d[15]),
      "+f"(d[16]), "+f"(d[17]), "+f"(d[18]), "+f"(d[19]), "+f"(d[20]), "+f"(d[21]), "+f"(d[22]), "+f"(d[23]),
      "+f"(d[24]), "+f"(d[25]), "+f"(d[26]), "+f"(d[27]), "+f"(d[28]), "+f"(d[29]), "+f"(d[30]), "+f"(d[31])
    : "r"(a0), "r"(a1), "r"(a2), "r"(a3), "l"(descB), "r"(scaleD));
}
__device__ __forceinline__ void wgmma_n32_rs_tb(float (&d)[16], uint32_t a0, uint32_t a1, uint32_t a2, uint32_t a3, uint64_t descB, int scaleD) {
  asm volatile("{\n.reg .pred p;\nsetp.ne.b32 p, %21, 0;\n"
    "wgmma.mma_async.sync.aligned.m64n32k16.f32.bf16.bf16 "
    "{%0, %1, %2, %3, %4, %5, %6, %7, %8, %9, %10, %11, %12, %13, %14, %15}, "
    "{%16, %17, %18, %19}, %20, p, 1, 1, 1;\n}\n"
    : "+f"(d[0]), "+f"(d[1]), "+f"(d[2]), "+f"(d[3]), "+f"(d[4]), "+f"(d[5]), "+f"(d[6]), "+f"(d[7]),
      "+f"(d[8]), "+f"(d[9]), "+f"(d[10]), "+f"(d[11]), "+f"(d[12]), "+f"(d[13]), "+f"(d[14]), "+f"(d[15])
    : "r"(a0), "r"(a1), "r"(a2), "r"(a3), "l"(descB), "r"(scaleD));
}

__device__ __forceinline__ void wg_fence() { asm volatile("wgmma.fence.sync.aligned;" ::: "memory"); }
__device__ __forceinline__ void wg_commit() { asm volatile("wgmma.commit_group.sync.aligned;" ::: "memory"); }
template <int N>
__device__ __forceinline__ void wg_wait() { asm volatile("wgmma.wait_group.sync.aligned %0;" ::"n"(N) : "memory"); }

template <int N>
__device__ __forceinline__ void reg_fence(float (&d)[N]) {
#pragma unroll
  for (int i = 0; i < N; i++) asm volatile("" : "+f"(d[i])::"memory");
}

__device__ __forceinline__ float ex2(float x) {
  float y;
  asm("ex2.approx.ftz.f32 %0, %1;" : "=f"(y) : "f"(x));
  return y;
}
__device__ __forceinline__ uint32_t pack_bf16(float lo, float hi) {
  uint32_t v;
  asm("cvt.rn.bf16x2.f32 %0, %1, %2;" : "=r"(v) : "f"(hi), "f"(lo));
  return v;
}
constexpr uint32_t DESC_SW128 = 0x40000040;
constexpr uint32_t DESC_SW64 = 0x80000020;
__device__ __forceinline__ uint32_t desc_lo(uint32_t saddr, uint32_t lbo) {
  return ((saddr & 0x3FFFF) >> 4) | ((lbo >> 4) << 16);
}
__device__ __forceinline__ uint64_t desc64(uint32_t lo, uint32_t hi) {
  uint64_t d;
  asm("mov.b64 %0, {%1, %2};" : "=l"(d) : "r"(lo), "r"(hi));
  return d;
}

__device__ __forceinline__ int opaque_tid() {
  int v;
  asm volatile("mov.u32 %0, %%tid.x;" : "=r"(v));
  return v;
}
__device__ __forceinline__ int opaque_cta() {
  int v;
  asm volatile("mov.u32 %0, %%ctaid.x;" : "=r"(v));
  return v;
}

constexpr uint32_t SPIN_LIMIT = 1u << 18;
constexpr uint32_t SUSPEND_NS = 20000;

__device__ __forceinline__ void mbar_init(uint32_t bar, uint32_t count) {
  asm volatile("mbarrier.init.shared::cta.b64 [%0], %1;" ::"r"(bar), "r"(count) : "memory");
}
__device__ __forceinline__ bool mbar_try(uint32_t bar, uint32_t parity) {
  uint32_t ok;
  asm volatile(
      "{\n.reg .pred p;\nmbarrier.try_wait.parity.shared::cta.b64 p, [%1], %2, %3;\nselp.u32 %0, 1, 0, p;\n}"
      : "=r"(ok)
      : "r"(bar), "r"(parity), "r"(SUSPEND_NS)
      : "memory");
  return ok != 0;
}
__device__ __forceinline__ void mbar_wait(uint32_t bar, uint32_t parity) {
  asm volatile(
      "{\n.reg .pred p;\nWAIT_LOOP:\nmbarrier.try_wait.parity.shared::cta.b64 p, [%0], %1;\n@p bra WAIT_DONE;\nbra "
      "WAIT_LOOP;\nWAIT_DONE:\n}" ::"r"(bar),
      "r"(parity)
      : "memory");
}
__device__ __forceinline__ uint32_t mbar_test(uint32_t bar, uint32_t parity) {
  uint32_t ok;
  asm volatile(
      "{\n.reg .pred p;\nmbarrier.test_wait.parity.shared::cta.b64 p, [%1], %2;\nselp.u32 %0, 1, 0, p;\n}"
      : "=r"(ok)
      : "r"(bar), "r"(parity)
      : "memory");
  return ok;
}
__device__ __forceinline__ void mbar_wait_spin(uint32_t bar, uint32_t parity) {
  uint32_t n = 0;
  while (true) {
    uint32_t ok;
    asm volatile(
        "{\n.reg .pred p;\nmbarrier.try_wait.parity.shared::cta.b64 p, [%1], %2;\nselp.u32 %0, 1, 0, p;\n}"
        : "=r"(ok)
        : "r"(bar), "r"(parity)
        : "memory");
    if (ok) break;
    if (++n > (1u << 24)) __trap();
  }
}
__device__ __forceinline__ void mbar_wait_bounded(uint32_t bar, uint32_t parity) {
  uint32_t n = 0;
  while (!mbar_try(bar, parity)) {
    if (++n > SPIN_LIMIT) __trap();
  }
}
__device__ __forceinline__ void mbar_expect_tx(uint32_t bar, uint32_t bytes) {
  asm volatile("mbarrier.arrive.expect_tx.shared::cta.b64 _, [%0], %1;" ::"r"(bar), "r"(bytes) : "memory");
}
__device__ __forceinline__ void mbar_arrive(uint32_t bar) {
  asm volatile("mbarrier.arrive.shared::cta.b64 _, [%0];" ::"r"(bar) : "memory");
}
__device__ __forceinline__ void mbar_arrive_pair_if(uint32_t local, uint32_t remote, bool pred) {
  asm volatile(
      "{\n.reg .pred p;\nsetp.ne.u32 p, %2, 0;\n@p mbarrier.arrive.shared::cta.b64 _, [%0];\n@p "
      "mbarrier.arrive.shared::cluster.b64 _, [%1];\n}" ::"r"(local),
      "r"(remote), "r"((uint32_t)pred)
      : "memory");
}
__device__ __forceinline__ uint32_t peer_addr(uint32_t addr) {
  uint32_t r;
  asm volatile("mapa.shared::cluster.u32 %0, %1, %2;" : "=r"(r) : "r"(addr), "r"((blockIdx.x & 1) ^ 1));
  return r;
}
__device__ __forceinline__ void tma_load(uint32_t dst, const CUtensorMap* tm, uint32_t bar, int c0, int c1) {
  asm volatile(
      "cp.async.bulk.tensor.2d.shared::cluster.global.mbarrier::complete_tx::bytes [%0], [%1, {%3, %4}], [%2];" ::"r"(dst),
      "l"(tm), "r"(bar), "r"(c0), "r"(c1)
      : "memory");
}
__device__ __forceinline__ void tma_load_mc(uint32_t dst, const CUtensorMap* tm, uint32_t bar, int c0, int c1) {
  asm volatile(
      "cp.async.bulk.tensor.2d.shared::cluster.global.mbarrier::complete_tx::bytes.multicast::cluster [%0], [%1, {%3, "
      "%4}], [%2], %5;" ::"r"(dst),
      "l"(tm), "r"(bar), "r"(c0), "r"(c1), "h"((uint16_t)3)
      : "memory");
}
__device__ __forceinline__ void bulk_load(uint32_t dst, const void* src, uint32_t bytes, uint32_t bar) {
  asm volatile("cp.async.bulk.shared::cluster.global.mbarrier::complete_tx::bytes [%0], [%1], %2, [%3];" ::"r"(dst),
               "l"(src), "r"(bytes), "r"(bar)
               : "memory");
}
__device__ __forceinline__ float lds_f32(uint32_t a) {
  float v;
  asm volatile("ld.shared.f32 %0, [%1];" : "=f"(v) : "r"(a) : "memory");
  return v;
}
__device__ __forceinline__ void tma_store(const CUtensorMap* tm, uint32_t src, int c0, int c1) {
  asm volatile("cp.async.bulk.tensor.2d.global.shared::cta.bulk_group [%0, {%2, %3}], [%1];" ::"l"(tm), "r"(src),
               "r"(c0), "r"(c1)
               : "memory");
}
__device__ __forceinline__ void fence_proxy_async_global() { asm volatile("fence.proxy.async.global;" ::: "memory"); }
__device__ __forceinline__ void fence_proxy_async_smem() { asm volatile("fence.proxy.async.shared::cta;" ::: "memory"); }
template <int ID>
__device__ __forceinline__ void bar_sync128() { asm volatile("bar.sync %0, 128;" ::"n"(ID) : "memory"); }
__device__ __forceinline__ void cluster_sync() {
  asm volatile("barrier.cluster.arrive.relaxed.aligned;\nbarrier.cluster.wait.aligned;" ::: "memory");
}
__device__ __forceinline__ void fence_gpu() { asm volatile("fence.acq_rel.gpu;" ::: "memory"); }
__device__ __forceinline__ void flag_add(int idx) {
  asm volatile("red.relaxed.gpu.global.add.u32 [%0], 1;" ::"l"(&g_flags[idx * 32]) : "memory");
}
__device__ __forceinline__ void warp_arrive(uint32_t bar, int lane) {
  __syncwarp();
  if (lane == 0) asm volatile("mbarrier.arrive.shared::cta.b64 _, [%0];" ::"r"(bar) : "memory");
}
__device__ __forceinline__ float rcp(float x) {
  float y;
  asm("rcp.approx.ftz.f32 %0, %1;" : "=f"(y) : "f"(x));
  return y;
}
__device__ __forceinline__ void flag_wait(int idx, unsigned target) {
  const unsigned* p = &g_flags[idx * 32];
  uint32_t n = 0;
  while (true) {
    unsigned v;
    asm volatile("ld.acquire.gpu.global.u32 %0, [%1];" : "=r"(v) : "l"(p) : "memory");
    if ((int)(v - target) >= 0) break;
    if (++n > (1u << 24)) __trap();
    __nanosleep(32);
  }
}
__device__ __forceinline__ void st_global_v4(void* p, uint32_t a, uint32_t b, uint32_t c, uint32_t d) {
  asm volatile("st.global.v4.b32 [%0], {%1, %2, %3, %4};" ::"l"(p), "r"(a), "r"(b), "r"(c), "r"(d) : "memory");
}
__device__ __forceinline__ void stmatrix_x4(uint32_t addr, uint32_t a, uint32_t b, uint32_t c, uint32_t d) {
  asm volatile("stmatrix.sync.aligned.m8n8.x4.shared.b16 [%0], {%1, %2, %3, %4};" ::"r"(addr), "r"(a), "r"(b), "r"(c),
               "r"(d)
               : "memory");
}
__device__ __forceinline__ void ldmatrix_x4(uint32_t addr, uint32_t& a, uint32_t& b, uint32_t& c, uint32_t& d) {
  asm volatile("ldmatrix.sync.aligned.m8n8.x4.shared.b16 {%0, %1, %2, %3}, [%4];"
               : "=r"(a), "=r"(b), "=r"(c), "=r"(d)
               : "r"(addr)
               : "memory");
}
__device__ __forceinline__ void red_add_v2(float* p, float a, float b) {
  asm volatile("red.relaxed.gpu.global.add.v2.f32 [%0], {%1, %2};" ::"l"(p), "f"(a), "f"(b) : "memory");
}
__device__ __forceinline__ void red_add(float* p, float a) {
  asm volatile("red.relaxed.gpu.global.add.f32 [%0], %1;" ::"l"(p), "f"(a) : "memory");
}
__device__ __forceinline__ void mma_16816(float (&d)[4], uint32_t a0, uint32_t a1, uint32_t a2, uint32_t a3, uint32_t b0,
                                          uint32_t b1) {
  asm volatile(
      "mma.sync.aligned.m16n8k16.row.col.f32.bf16.bf16.f32 {%0, %1, %2, %3}, {%4, %5, %6, %7}, {%8, %9}, {%0, %1, %2, "
      "%3};"
      : "+f"(d[0]), "+f"(d[1]), "+f"(d[2]), "+f"(d[3])
      : "r"(a0), "r"(a1), "r"(a2), "r"(a3), "r"(b0), "r"(b1));
}
__device__ __forceinline__ float phi(float t) {
  return (fmaxf(t, 0.f) + 1e-6f) + ex2(fminf(t * 1.4426950408889634f, 0.f));
}

constexpr int N_TILES = 8;

__device__ __forceinline__ int tile_kind(int pos, int rt) { return pos < 6 ? pos : (rt < 8 ? 6 : 7); }
__device__ __forceinline__ int tile_rt(int pos, int rt) {
  return pos < 6 ? rt : (rt < 8 ? (pos == 6 ? rt : rt + 8) : (pos == 6 ? rt - 8 : rt));
}

__device__ __forceinline__ void gemm_mainloop(float (&c0)[64], float (&c1)[64], uint32_t sb, uint32_t& it, bool elected) {
  const uint32_t bars = sb + OFF_BAR;
#pragma unroll
  for (int i = 0; i < 64; i++) c0[i] = c1[i] = 0.f;
  reg_fence(c0);
  reg_fence(c1);
  wg_fence();
  const uint32_t dA0 = desc_lo(sb, 16), dB0 = desc_lo(sb + 16384, 8192);
  const uint32_t empty_l = bars + 8 * B_GEMPTY, empty_r = peer_addr(empty_l);
#pragma unroll 1
  for (int kb = 0; kb < 16; kb++, it++) {
    const uint32_t s = it & (G_STAGES - 1);
    mbar_wait(bars + 8 * (B_GFULL + s), (it / G_STAGES) & 1);
    const uint64_t dA = desc64(dA0 + s * (G_SLOT >> 4), DESC_SW128), dB = desc64(dB0 + s * (G_SLOT >> 4), DESC_SW128);
#pragma unroll
    for (int kk = 0; kk < 4; kk++) {
      wgmma_n128_ss_tb(c0, dA + kk * 2, dB + kk * 128, 1);
      wg_commit();
      wg_wait<1>();
      if (kk == 0) {
        const uint32_t e = 8 * ((it - 1) & (G_STAGES - 1));
        mbar_arrive_pair_if(empty_l + e, empty_r + e, elected && kb > 0);
      }
      wgmma_n128_ss_tb(c1, dA + 512 + kk * 2, dB + kk * 128, 1);
      wg_commit();
      wg_wait<1>();
    }
  }
  wg_wait<0>();
  reg_fence(c0);
  reg_fence(c1);
  const uint32_t e = 8 * ((it - 1) & (G_STAGES - 1));
  mbar_arrive_pair_if(empty_l + e, empty_r + e, elected);
}

template <int B0, bool PHI>
__device__ __forceinline__ void stage_block(const float (&c)[64], uint32_t piece, int warp, int lane) {
  const int r = warp * 16 + (lane & 7) + ((lane >> 3) & 1) * 8;
  const uint32_t rowaddr = piece + r * 128;
#pragma unroll
  for (int b = 0; b < 8; b += 2) {
    float v[8];
#pragma unroll
    for (int i = 0; i < 8; i++) v[i] = PHI ? phi(c[4 * (B0 + b) + i]) : c[4 * (B0 + b) + i];
    const uint32_t chunk = (uint32_t)(b + (lane >> 4)) ^ (uint32_t)(lane & 7);
    stmatrix_x4(rowaddr + chunk * 16, pack_bf16(v[0], v[1]), pack_bf16(v[2], v[3]), pack_bf16(v[4], v[5]),
                pack_bf16(v[6], v[7]));
  }
}

__device__ __forceinline__ int qkv_box_col(int b) { return (b % 3) * 1024 + (b / 3) * 64; }

template <int B0, bool SCALE>
__device__ __forceinline__ void epi_qkvA_store(const float (&c0)[64], const float (&c1)[64], __nv_bfloat16* base) {
  const float sc = 0.25503486164812727f;
#pragma unroll
  for (int mb = 0; mb < 2; mb++) {
#pragma unroll
    for (int hh = 0; hh < 2; hh++) {
#pragma unroll
      for (int h8 = 0; h8 < 2; h8++) {
        uint32_t w[4];
#pragma unroll
        for (int j = 0; j < 4; j++) {
          const int r = 4 * (B0 + hh * 4 + j) + 2 * h8;
          const float a = mb == 0 ? c0[r] : c1[r], b = mb == 0 ? c0[r + 1] : c1[r + 1];
          w[j] = SCALE ? pack_bf16(a * sc, b * sc) : pack_bf16(a, b);
        }
        st_global_v4(base + (size_t)hh * SEQ * 32 + (mb * 64 + h8 * 8) * 32, w[0], w[1], w[2], w[3]);
      }
    }
  }
}
template <int B0>
__device__ __forceinline__ void epi_qkvA(const float (&c0)[64], const float (&c1)[64], int row0, int box, int warp,
                                         int lane) {
  const int part = box % 3, hp = box / 3;
  __nv_bfloat16* base =
      g_qkvA + ((size_t)(part * 32 + hp * 2) * SEQ + row0 + warp * 16 + (lane >> 2)) * 32 + (lane & 3) * 8;
  if (part == 0)
    epi_qkvA_store<B0, true>(c0, c1, base);
  else
    epi_qkvA_store<B0, false>(c0, c1, base);
}

__device__ __forceinline__ void epi_qB_issue(float (&d0)[20], float (&d1)[20], uint32_t piece, uint32_t kvz) {
  const uint64_t dA = desc64(desc_lo(piece, 16), DESC_SW128), dB = desc64(desc_lo(kvz, 16), DESC_SW64);
  wg_fence();
  wgmma_n40_ss(d0, dA, dB, 0);
  wgmma_n40_ss(d0, dA + 2, dB + 2, 1);
  wgmma_n40_ss(d1, dA + 4, dB + 160, 0);
  wgmma_n40_ss(d1, dA + 6, dB + 162, 1);
  wg_commit();
}
__device__ __forceinline__ void epi_qB_store(float (&d)[20], __nv_bfloat16* dst) {
  reg_fence(d);
  const float i0 = rcp(d[16] + 1e-6f), i1 = rcp(d[18] + 1e-6f);
  st_global_v4(dst, pack_bf16(d[0] * i0, d[1] * i0), pack_bf16(d[4] * i0, d[5] * i0), pack_bf16(d[8] * i0, d[9] * i0),
               pack_bf16(d[12] * i0, d[13] * i0));
  st_global_v4(dst + 8 * DM, pack_bf16(d[2] * i1, d[3] * i1), pack_bf16(d[6] * i1, d[7] * i1),
               pack_bf16(d[10] * i1, d[11] * i1), pack_bf16(d[14] * i1, d[15] * i1));
}
__device__ __forceinline__ void epi_qB(uint32_t p0, uint32_t kvz, __nv_bfloat16* dst) {
  float a0[20], a1[20], b0[20], b1[20];
#pragma unroll
  for (int i = 0; i < 20; i++) a0[i] = a1[i] = b0[i] = b1[i] = 0.f;
  reg_fence(a0);
  reg_fence(a1);
  reg_fence(b0);
  reg_fence(b1);
  epi_qB_issue(a0, a1, p0, kvz);
  epi_qB_issue(b0, b1, p0 + STG, kvz + 5120);
  wg_wait<1>();
  epi_qB_store(a0, dst);
  epi_qB_store(a1, dst + 32);
  epi_qB_issue(a0, a1, p0 + 2 * STG, kvz);
  wg_wait<1>();
  epi_qB_store(b0, dst + 64);
  epi_qB_store(b1, dst + 96);
  epi_qB_issue(b0, b1, p0 + 3 * STG, kvz + 5120);
  wg_wait<1>();
  epi_qB_store(a0, dst + 64 * DM);
  epi_qB_store(a1, dst + 64 * DM + 32);
  wg_wait<0>();
  epi_qB_store(b0, dst + 64 * DM + 64);
  epi_qB_store(b1, dst + 64 * DM + 96);
}

__device__ __forceinline__ void gemm_consumer(const Params& P, uint32_t sb, unsigned epoch) {
  const bool elected = (threadIdx.x & 127) == 0;
  const uint32_t bars = sb + OFF_BAR;
  uint32_t it = 0;
#pragma unroll 1
  for (int pos = 0; pos < N_TILES; pos++) {
    float c0[64], c1[64];
    gemm_mainloop(c0, c1, sb, it, elected);
    const int tid = opaque_tid() & 127, cta = opaque_cta();
    const int warp = tid >> 5, lane = tid & 31;
    const int rt = 2 * ((cta >> 1) & 7) + (cta & 1), grp = cta >> 4;
    const int t = tile_kind(pos, rt);
    const int row0 = tile_rt(pos, rt) * 128;
    const uint32_t p0 = sb + OFF_STG, p1 = p0 + STG, p2 = p1 + STG, p3 = p2 + STG;
    if (t < 3) {
      const int box = 2 * (8 * t + grp);
      epi_qkvA<0>(c0, c1, row0, box, warp, lane);
      epi_qkvA<8>(c0, c1, row0, box + 1, warp, lane);
      warp_arrive(bars + 8 * (B_GSIG + t), lane);
    } else if (t < 5) {
      const int hp = grp + 8 * (t - 3);
      stage_block<0, true>(c0, p0, warp, lane);
      stage_block<0, true>(c1, p1, warp, lane);
      stage_block<8, false>(c0, p2, warp, lane);
      stage_block<8, false>(c1, p3, warp, lane);
      fence_proxy_async_smem();
      bar_sync128<1>();
      float d[36];
#pragma unroll
      for (int i = 0; i < 36; i++) d[i] = 0.f;
      reg_fence(d);
      wg_fence();
      const uint32_t ones = sb + OFF_KVZ;
#pragma unroll
      for (int s = 0; s < 8; s++) {
        const uint32_t pa = (s < 4 ? p0 : p1) + (s & 3) * 2048;
        const uint32_t pb = (s < 4 ? p2 : p3) + (s & 3) * 2048;
        wgmma_n72_ss_ta_tb(d, desc64(desc_lo(pa, 8192), DESC_SW128), desc64(desc_lo(pb, ones - pb), DESC_SW128), s > 0);
      }
      wg_commit();
      wg_wait<0>();
      reg_fence(d);
      const int par = epoch & 1;
      const int g = lane >> 2, q4 = lane & 3;
      const int h = hp * 2 + (warp >> 1);
      const int dk = (warp & 1) * 16 + g;
      float* kvp = &g_kv[par][(h * 32 + dk) * 32 + 2 * q4];
      if (warp < 2) {
#pragma unroll
        for (int j = 0; j < 4; j++) {
          red_add_v2(kvp + 8 * j, d[4 * j], d[4 * j + 1]);
          red_add_v2(kvp + 8 * j + 8 * 32, d[4 * j + 2], d[4 * j + 3]);
        }
      } else {
#pragma unroll
        for (int j = 0; j < 4; j++) {
          red_add_v2(kvp + 8 * j, d[16 + 4 * j], d[16 + 4 * j + 1]);
          red_add_v2(kvp + 8 * j + 8 * 32, d[16 + 4 * j + 2], d[16 + 4 * j + 3]);
        }
      }
      if (q4 == 0) {
        red_add(&g_z[par][h * 32 + dk], d[32]);
        red_add(&g_z[par][h * 32 + dk + 8], d[34]);
      }
      warp_arrive(bars + 8 * (B_GSIG + t), lane);
    } else if (t == 5) {
      mbar_wait(bars + 8 * B_KVZ, 0);
      stage_block<0, true>(c0, p0, warp, lane);
      stage_block<8, true>(c0, p1, warp, lane);
      stage_block<0, true>(c1, p2, warp, lane);
      stage_block<8, true>(c1, p3, warp, lane);
      fence_proxy_async_smem();
      bar_sync128<1>();
      __nv_bfloat16* dst = g_oB + (size_t)(row0 + warp * 16 + (lane >> 2)) * DM + grp * 128 + (lane & 3) * 8;
      epi_qB(p0, sb + OFF_KVZ, dst);
      warp_arrive(bars + 8 * (B_GSIG + t), lane);
    } else {
      if (elected) asm volatile("cp.async.bulk.wait_group.read 0;" ::: "memory");
      bar_sync128<1>();
      stage_block<0, false>(c0, p0, warp, lane);
      stage_block<8, false>(c0, p1, warp, lane);
      stage_block<0, false>(c1, p2, warp, lane);
      stage_block<8, false>(c1, p3, warp, lane);
      fence_proxy_async_smem();
      bar_sync128<1>();
      if (elected) {
        const int col = (t == 6 ? DM : 0) + grp * 128;
        tma_store(&P.out, p0, col, row0);
        tma_store(&P.out, p1, col + 64, row0);
        tma_store(&P.out, p2, col, row0 + 64);
        tma_store(&P.out, p3, col + 64, row0 + 64);
        asm volatile("cp.async.bulk.commit_group;" ::: "memory");
      }
    }
  }
  if (elected) asm volatile("cp.async.bulk.wait_group.read 0;" ::: "memory");
}

__device__ __forceinline__ void gemm_producer(const Params& P, uint32_t sb, int pair, int rank, unsigned epoch) {
  const int rt_own = 2 * (pair & 7) + rank;
  const int grp = pair >> 3;
  const uint32_t bars = sb + OFF_BAR;
  uint32_t it = 0;
#pragma unroll 1
  for (int pos = 0; pos < N_TILES; pos++) {
    const int t = tile_kind(pos, rt_own);
    const int rt = tile_rt(pos, rt_own);
    const int row0 = rt * 128;
    const CUtensorMap* ta = t < 3 ? &P.xA : t < 6 ? &P.xB : t == 6 ? &P.oB : &P.oA;
    const CUtensorMap* tb = t < 3 ? &P.wA : t < 6 ? &P.wB : t == 6 ? &P.woB : &P.woA;
    int col0, col1;
    if (t < 3) {
      const int box = 2 * (8 * t + grp);
      col0 = qkv_box_col(box), col1 = qkv_box_col(box + 1);
    } else if (t < 5) {
      col0 = 1024 + (grp + 8 * (t - 3)) * 64, col1 = col0 + 1024;
    } else {
      col0 = grp * 128, col1 = col0 + 64;
    }
    if (t == 6) {
      flag_wait(F_OB + rt, (epoch + 1) * 8);
      fence_proxy_async_global();
    } else if (t == 7) {
      flag_wait(F_OA + rt, (epoch + 1) * 16);
      fence_proxy_async_global();
    }
#pragma unroll 1
    for (int kb = 0; kb < 16; kb++, it++) {
      if (t == 7 && kb == 8) {
        flag_wait(F_OA2 + rt, (epoch + 1) * 16);
        fence_proxy_async_global();
      }
      const int kc = kb * 64;
      const uint32_t s = it & (G_STAGES - 1);
      mbar_wait_spin(bars + 8 * (B_GEMPTY + s), ((it / G_STAGES) & 1) ^ 1);
      const uint32_t full = bars + 8 * (B_GFULL + s);
      const uint32_t slot = sb + s * G_SLOT;
      mbar_expect_tx(full, 32768);
      tma_load(slot, ta, full, kc, row0);
      if ((kb & 1) == rank) {
        tma_load_mc(slot + 16384, tb, full, col0, kc);
        tma_load_mc(slot + 24576, tb, full, col1, kc);
      }
    }
  }
}

__device__ __forceinline__ void attn_task(int r, int pair, int rank, int& head, int& qt) {
  if (r < 2) {
    head = (pair >> 3) + 8 * r;
    qt = 2 * (pair & 7) + rank;
  } else {
    head = 16 + (pair >> 2);
    qt = 8 * (r - 2) + 2 * (pair & 3) + rank;
  }
}

__device__ __forceinline__ void attn_producer(const Params& P, uint32_t sb, int pair, int rank, unsigned epoch) {
  const uint32_t bars = sb + OFF_BAR;
  uint32_t st = 0, ph = 1;
#pragma unroll 1
  for (int r = 0; r < 4; r++) {
    int head, qt;
    attn_task(r, pair, rank, head, qt);
    flag_wait(F_QKVA + (head >> 1), (epoch + 1) * 48);
    fence_proxy_async_global();
    mbar_wait_spin(bars + 8 * B_QEMPTY, (r & 1) ^ 1);
    mbar_expect_tx(bars + 8 * B_QFULL, 8192);
    tma_load(sb + OFF_Q, &P.qkv, bars + 8 * B_QFULL, 0, head * SEQ + qt * 128);
    const int row = ((rank + 1) * 32 + head) * SEQ;
#pragma unroll 1
    for (int j = 0; j < 16; j++) {
      const uint32_t slot = sb + OFF_A + st * A_SLOT;
      mbar_wait_spin(bars + 8 * (B_KEMPTY + st), ph);
      mbar_expect_tx(bars + 8 * (B_KFULL + st), 8192);
      if (rank == 0) tma_load_mc(slot, &P.qkv, bars + 8 * (B_KFULL + st), 0, row + j * 128);
      mbar_wait_spin(bars + 8 * (B_VEMPTY + st), ph);
      mbar_expect_tx(bars + 8 * (B_VFULL + st), 8192);
      if (rank == 1) tma_load_mc(slot + 8192, &P.qkv, bars + 8 * (B_VFULL + st), 0, row + j * 128);
      if (++st == A_STAGES) st = 0, ph ^= 1;
    }
  }
}

__device__ __forceinline__ void attn_slow(int row0, int head, int lane, float (&o)[16], float& l0, float& l1) {
  const int g = lane >> 2, t = lane & 3;
  uint32_t q[8];
  {
    const uint32_t* qr = reinterpret_cast<const uint32_t*>(g_qkvA + ((size_t)head * SEQ + row0 + g) * 32);
#pragma unroll
    for (int i = 0; i < 8; i++) q[i] = __ldcg(qr + (i & 1) * 8 * 16 + (i >> 1) * 4 + t);
  }
  const __nv_bfloat16* K = g_qkvA + (size_t)(32 + head) * SEQ * 32;
  const unsigned short* V = reinterpret_cast<const unsigned short*>(g_qkvA + (size_t)(64 + head) * SEQ * 32);
  float m0 = -INFINITY, m1 = -INFINITY;
  float acc[4][4];
#pragma unroll
  for (int i = 0; i < 4; i++)
#pragma unroll
    for (int j = 0; j < 4; j++) acc[i][j] = 0.f;
  l0 = l1 = 0.f;
#pragma unroll 1
  for (int k0 = 0; k0 < SEQ; k0 += 16) {
    float s[2][4];
#pragma unroll
    for (int nb = 0; nb < 2; nb++) {
      s[nb][0] = s[nb][1] = s[nb][2] = s[nb][3] = 0.f;
      const uint32_t* kr = reinterpret_cast<const uint32_t*>(K + (size_t)(k0 + nb * 8 + g) * 32);
#pragma unroll
      for (int ks = 0; ks < 2; ks++)
        mma_16816(s[nb], q[4 * ks], q[4 * ks + 1], q[4 * ks + 2], q[4 * ks + 3], __ldcg(kr + ks * 8 + t),
                  __ldcg(kr + ks * 8 + 4 + t));
    }
    float x0 = fmaxf(fmaxf(s[0][0], s[0][1]), fmaxf(s[1][0], s[1][1]));
    float x1 = fmaxf(fmaxf(s[0][2], s[0][3]), fmaxf(s[1][2], s[1][3]));
    x0 = fmaxf(x0, __shfl_xor_sync(0xffffffffu, x0, 1));
    x0 = fmaxf(x0, __shfl_xor_sync(0xffffffffu, x0, 2));
    x1 = fmaxf(x1, __shfl_xor_sync(0xffffffffu, x1, 1));
    x1 = fmaxf(x1, __shfl_xor_sync(0xffffffffu, x1, 2));
    const float n0 = fmaxf(m0, x0), n1 = fmaxf(m1, x1);
    const float a0 = ex2(m0 - n0), a1 = ex2(m1 - n1);
    m0 = n0, m1 = n1;
    float p[2][4];
#pragma unroll
    for (int nb = 0; nb < 2; nb++) {
      p[nb][0] = ex2(s[nb][0] - n0), p[nb][1] = ex2(s[nb][1] - n0);
      p[nb][2] = ex2(s[nb][2] - n1), p[nb][3] = ex2(s[nb][3] - n1);
    }
    l0 = l0 * a0 + (p[0][0] + p[0][1]) + (p[1][0] + p[1][1]);
    l1 = l1 * a1 + (p[0][2] + p[0][3]) + (p[1][2] + p[1][3]);
    const uint32_t pa0 = pack_bf16(p[0][0], p[0][1]), pa1 = pack_bf16(p[0][2], p[0][3]);
    const uint32_t pa2 = pack_bf16(p[1][0], p[1][1]), pa3 = pack_bf16(p[1][2], p[1][3]);
#pragma unroll
    for (int nb = 0; nb < 4; nb++) {
      acc[nb][0] *= a0, acc[nb][1] *= a0, acc[nb][2] *= a1, acc[nb][3] *= a1;
      const unsigned short* vr = V + (size_t)(k0 + 2 * t) * 32 + nb * 8 + g;
      const uint32_t b0 = (uint32_t)__ldcg(vr) | ((uint32_t)__ldcg(vr + 32) << 16);
      const uint32_t b1 = (uint32_t)__ldcg(vr + 8 * 32) | ((uint32_t)__ldcg(vr + 9 * 32) << 16);
      mma_16816(acc[nb], pa0, pa1, pa2, pa3, b0, b1);
    }
  }
#pragma unroll
  for (int i = 0; i < 4; i++)
#pragma unroll
    for (int j = 0; j < 4; j++) o[4 * i + j] = acc[i][j];
}

__device__ __forceinline__ void attn_qk(float (&s)[32], const uint32_t (&q)[8], uint64_t dk) {
  wg_fence();
  wgmma_n64_rs(s, q[0], q[1], q[2], q[3], dk, 0);
  wgmma_n64_rs(s, q[4], q[5], q[6], q[7], dk + 2, 1);
  wg_commit();
}
template <int B>
__device__ __forceinline__ void attn_exp(float (&s)[32]) {
#pragma unroll
  for (int i = 0; i < 16; i++) s[B + i] = ex2(s[B + i]);
}
template <int B>
__device__ __forceinline__ void attn_pv(float (&o)[16], const float (&s)[32], uint64_t dv, float (&l)[4]) {
  uint32_t p[8];
#pragma unroll
  for (int i = 0; i < 8; i++) p[i] = pack_bf16(s[B + 2 * i], s[B + 2 * i + 1]);
#pragma unroll
  for (int i = 0; i < 16; i++) l[i & 3] += s[B + i];
  asm volatile("" : "+f"(l[0]), "+f"(l[1]), "+f"(l[2]), "+f"(l[3]));
  wg_fence();
  wgmma_n32_rs_tb(o, p[0], p[1], p[2], p[3], dv, 1);
  wgmma_n32_rs_tb(o, p[4], p[5], p[6], p[7], dv + 64, 1);
  wg_commit();
}
constexpr int NE = 8;
__device__ __forceinline__ void attn_pv_first(float (&o)[16], const float (&e)[NE], const float (&s)[32], uint64_t dv,
                                              float (&l)[4]) {
  uint32_t p[8];
#pragma unroll
  for (int i = 0; i < 8; i++)
    p[i] = 2 * i < NE ? pack_bf16(e[(2 * i) % NE], e[(2 * i + 1) % NE]) : pack_bf16(s[2 * i], s[2 * i + 1]);
#pragma unroll
  for (int i = 0; i < 16; i++) l[i & 3] += i < NE ? e[i % NE] : s[i];
  asm volatile("" : "+f"(l[0]), "+f"(l[1]), "+f"(l[2]), "+f"(l[3]));
  wg_fence();
  wgmma_n32_rs_tb(o, p[0], p[1], p[2], p[3], dv, 1);
  wgmma_n32_rs_tb(o, p[4], p[5], p[6], p[7], dv + 64, 1);
  wg_commit();
}

__device__ __forceinline__ void attn_load_q(uint32_t sb, uint32_t (&q)[8]) {
  const int tid = opaque_tid();
  const int lane = tid & 31;
  const int row = ((tid >> 5) - 8) * 16 + (lane & 7) + ((lane >> 3) & 1) * 8;
  const uint32_t ra = sb + OFF_Q + row * 64;
  const uint32_t sw = (row >> 1) & 3;
  ldmatrix_x4(ra + (((lane >> 4)) ^ sw) * 16, q[0], q[1], q[2], q[3]);
  ldmatrix_x4(ra + ((2 + (lane >> 4)) ^ sw) * 16, q[4], q[5], q[6], q[7]);
  warp_arrive(sb + OFF_BAR + 8 * B_QEMPTY, lane);
}

template <bool LAST>
__device__ __forceinline__ void attn_stage(uint32_t sb, uint32_t bars_r, uint32_t dk0, bool elected, bool has_next,
                                           bool force_k, bool release_prev, uint32_t& st, uint32_t& ph, uint32_t& ready,
                                           uint32_t (&q)[8], float (&o)[16], float (&s0)[32], float (&s1)[32],
                                           float (&e)[NE], float (&l)[4], uint32_t qph) {
  const uint32_t bars = sb + OFF_BAR;
  const uint32_t nst = st == A_STAGES - 1 ? 0 : st + 1;
  const uint32_t nph = st == A_STAGES - 1 ? ph ^ 1 : ph;
  const uint32_t pst = st == 0 ? A_STAGES - 1 : st - 1;
  if (!ready) {
    mbar_wait(bars + 8 * (B_VFULL + st), ph);
    if (!LAST || has_next) mbar_wait(bars + 8 * (B_KFULL + nst), nph);
  }
  const uint64_t dk = desc64(dk0 + st * (A_SLOT >> 4), DESC_SW64), dv = dk + 512;
  const uint64_t dkn = desc64(dk0 + (!LAST || has_next ? nst : st) * (A_SLOT >> 4), DESC_SW64);
  attn_qk(s1, q, dk + 256);
#pragma unroll
  for (int i = NE; i < 16; i++) s0[i] = ex2(s0[i]);
  wg_wait<1>();
  mbar_arrive_pair_if(bars + 8 * (B_VEMPTY + pst), bars_r + 8 * (B_VEMPTY + pst), elected && release_prev);
  attn_pv_first(o, e, s0, dv, l);
  attn_exp<16>(s0);
  wg_wait<1>();
  mbar_arrive_pair_if(bars + 8 * (B_KEMPTY + st), bars_r + 8 * (B_KEMPTY + st), elected);
  if (LAST && has_next) {
    mbar_wait(bars + 8 * B_QFULL, qph);
    attn_load_q(sb, q);
  }
  attn_pv<16>(o, s0, dv + 128, l);
  attn_qk(s0, q, dkn);
  attn_exp<0>(s1);
  wg_wait<1>();
  attn_pv<0>(o, s1, dv + 256, l);
  {
    const uint32_t pph = st == 0 ? ph : ph ^ 1;
    ready = mbar_test(bars + 8 * (B_VFULL + nst), nph) & (mbar_test(bars + 8 * (B_KFULL + pst), pph) | force_k);
  }
  attn_exp<16>(s1);
  wg_wait<1>();
  reg_fence(s0);
#pragma unroll
  for (int i = 0; i < NE; i++) e[i] = ex2(s0[i]);
  wg_wait<0>();
  attn_pv<16>(o, s1, dv + 384, l);
  st = nst, ph = nph;
}

__device__ __forceinline__ void attn_consumer(uint32_t sb) {
  const uint32_t bars = sb + OFF_BAR;
  const uint32_t dk0 = desc_lo(sb + OFF_A, 16);
  const uint32_t bars_r = peer_addr(bars);
  const bool elected = (threadIdx.x & 127) == 0;
  uint32_t st = 0, ph = 0;
  uint32_t ready = 0;
  uint32_t q[8];
  float o[16], s0[32], s1[32], e[NE];
#pragma unroll
  for (int i = 0; i < 32; i++) s0[i] = s1[i] = 0.f;
  reg_fence(s0);
  reg_fence(s1);
  mbar_wait(bars + 8 * B_QFULL, 0);
  attn_load_q(sb, q);
  mbar_wait(bars + 8 * B_KFULL, 0);
  attn_qk(s0, q, desc64(dk0, DESC_SW64));
  wg_wait<0>();
  reg_fence(s0);
#pragma unroll
  for (int i = 0; i < NE; i++) e[i] = ex2(s0[i]);
#pragma unroll 1
  for (int r = 0; r < 4; r++) {
    float l[4] = {0.f, 0.f, 0.f, 0.f};
#pragma unroll
    for (int i = 0; i < 16; i++) o[i] = 0.f;
    reg_fence(o);
#pragma unroll 1
    for (int j = 0; j < 15; j++)
      attn_stage<false>(sb, bars_r, dk0, elected, true, j == 14 && r == 3, j > 0, st, ph, ready, q, o, s0, s1, e, l, 0);
    attn_stage<true>(sb, bars_r, dk0, elected, r < 3, false, true, st, ph, ready, q, o, s0, s1, e, l, (r + 1) & 1);
    wg_wait<0>();
    reg_fence(o);
    {
      const uint32_t pst = st == 0 ? A_STAGES - 1 : st - 1;
      mbar_arrive_pair_if(bars + 8 * (B_VEMPTY + pst), bars_r + 8 * (B_VEMPTY + pst), elected);
    }

    const int tid = opaque_tid(), cta = opaque_cta();
    const int lane = tid & 31;
    int head, qt;
    attn_task(r, cta >> 1, cta & 1, head, qt);
    const int row0 = qt * 128 + ((tid >> 5) - 8) * 16;
    float l0 = l[0] + l[1], l1 = l[2] + l[3];
    l0 += __shfl_xor_sync(0xffffffffu, l0, 1);
    l0 += __shfl_xor_sync(0xffffffffu, l0, 2);
    l1 += __shfl_xor_sync(0xffffffffu, l1, 1);
    l1 += __shfl_xor_sync(0xffffffffu, l1, 2);
    bool ok = l0 >= 0x1p-10f && l0 <= 0x1p60f && l1 >= 0x1p-10f && l1 <= 0x1p60f;
#pragma unroll
    for (int i = 0; i < 16; i++) ok = ok && fabsf(o[i]) <= 3.0e38f;
    if (__any_sync(0xffffffffu, !ok)) {
      attn_slow(row0, head, lane, o, l0, l1);
      l0 += __shfl_xor_sync(0xffffffffu, l0, 1);
      l0 += __shfl_xor_sync(0xffffffffu, l0, 2);
      l1 += __shfl_xor_sync(0xffffffffu, l1, 1);
      l1 += __shfl_xor_sync(0xffffffffu, l1, 2);
    }
    const float i0 = rcp(l0), i1 = rcp(l1);
    __nv_bfloat16* dst = g_oA + (size_t)(row0 + (lane >> 2)) * DM + head * 32 + (lane & 3) * 8;
    st_global_v4(dst, pack_bf16(o[0] * i0, o[1] * i0), pack_bf16(o[4] * i0, o[5] * i0), pack_bf16(o[8] * i0, o[9] * i0),
                 pack_bf16(o[12] * i0, o[13] * i0));
    st_global_v4(dst + 8 * DM, pack_bf16(o[2] * i1, o[3] * i1), pack_bf16(o[6] * i1, o[7] * i1),
                 pack_bf16(o[10] * i1, o[11] * i1), pack_bf16(o[14] * i1, o[15] * i1));
    warp_arrive(bars + 8 * (B_ASIG + r), lane);
  }
}

__device__ __forceinline__ void utility_gemm(uint32_t sb, int lane, int pair, unsigned epoch) {
  const uint32_t bars = sb + OFF_BAR;
  const int grp = pair >> 3, rt = 2 * (pair & 7) + (int)(blockIdx.x & 1);
  if (lane == 0) {
#pragma unroll 1
    for (int t = 0; t < 5; t++) {
      mbar_wait_spin(bars + 8 * (B_GSIG + t), 0);
      fence_gpu();
      if (t < 3) {
        const int box = 2 * (8 * t + grp);
        flag_add(F_QKVA + box / 3);
        flag_add(F_QKVA + (box + 1) / 3);
      } else {
        flag_add(F_KVB + grp + 8 * (t - 3));
      }
    }
    flag_wait(F_KVB + 2 * grp, (epoch + 1) * 16);
    flag_wait(F_KVB + 2 * grp + 1, (epoch + 1) * 16);
  }
  const int par = epoch & 1;
  const uint32_t p0 = sb + OFF_STG, p1 = p0 + STG, p2 = p1 + STG;
  if (lane == 0) {
    fence_proxy_async_global();
    const uint32_t bar = bars + 8 * B_KVLD;
    mbar_expect_tx(bar, 16384 + 512);
    bulk_load(p0, &g_kv[par][(4 * grp) * 1024], 8192, bar);
    bulk_load(p1, &g_kv[par][(4 * grp + 2) * 1024], 8192, bar);
    bulk_load(p2, &g_z[par][4 * grp * 32], 512, bar);
  }
  __syncwarp();
  mbar_wait_spin(bars + 8 * B_KVLD, 0);
  const int dv = 8 * ((lane >> 1) & 3) + 2 * (lane >> 3) + (lane & 1);
#pragma unroll 1
  for (int hh = 0; hh < 4; hh++) {
    const uint32_t base = sb + OFF_KVZ + hh * 2560;
    const uint32_t src = (hh < 2 ? p0 : p1) + (hh & 1) * 4096 + dv * 4;
#pragma unroll 4
    for (int k2 = 0; k2 < 16; k2++) {
      const uint32_t w = pack_bf16(lds_f32(src + k2 * 256), lds_f32(src + k2 * 256 + 128));
      const uint32_t a = base + lane * 64 + ((((uint32_t)k2 >> 2) ^ ((lane >> 1) & 3)) << 4) + (k2 & 3) * 4;
      asm volatile("st.shared.b32 [%0], %1;" ::"r"(a), "r"(w) : "memory");
    }
    const int k2 = lane & 15;
    const uint32_t w = pack_bf16(lds_f32(p2 + hh * 128 + k2 * 8), lds_f32(p2 + hh * 128 + k2 * 8 + 4));
#pragma unroll
    for (int rr = 0; rr < 4; rr++) {
      const uint32_t n = 32 + (lane >> 4) * 4 + rr;
      const uint32_t a = base + n * 64 + ((((uint32_t)k2 >> 2) ^ ((n >> 1) & 3)) << 4) + (k2 & 3) * 4;
      asm volatile("st.shared.b32 [%0], %1;" ::"r"(a), "r"(w) : "memory");
    }
  }
  fence_proxy_async_smem();
  __syncwarp();
  if (lane == 0) {
    mbar_arrive(bars + 8 * B_KVZ);
    mbar_wait_spin(bars + 8 * (B_GSIG + 5), 0);
    fence_gpu();
    flag_add(F_OB + rt);
  }
}
__device__ __forceinline__ void utility_attn(uint32_t sb, int lane, int cta, unsigned epoch) {
  const uint32_t bars = sb + OFF_BAR;
  const int par = epoch & 1;
  float4* kz = reinterpret_cast<float4*>(&g_kv[par ^ 1][cta * 256]);
  kz[lane] = make_float4(0.f, 0.f, 0.f, 0.f);
  kz[32 + lane] = make_float4(0.f, 0.f, 0.f, 0.f);
  if (lane < 2) reinterpret_cast<float4*>(&g_z[par ^ 1][cta * 8])[lane] = make_float4(0.f, 0.f, 0.f, 0.f);
  if (lane == 0) {
#pragma unroll 1
    for (int r = 0; r < 4; r++) {
      int head, qt;
      attn_task(r, cta >> 1, cta & 1, head, qt);
      mbar_wait_spin(bars + 8 * (B_ASIG + r), 0);
      fence_gpu();
      flag_add((r < 2 ? F_OA : F_OA2) + qt);
    }
    mbar_wait_bounded(bars + 8 * B_DONE, 0);
  }
}

__global__ void __cluster_dims__(2, 1, 1) __launch_bounds__(512) fused_kernel(const __grid_constant__ Params P) {
  extern __shared__ __align__(1024) uint8_t smem_raw[];
  const uint32_t sb = (uint32_t)__cvta_generic_to_shared(smem_raw);
  const int cta = blockIdx.x;
  const int pair = cta >> 1, rank = cta & 1;
  const int wgid = __shfl_sync(0xffffffffu, (int)(threadIdx.x >> 7), 0);
  const unsigned epoch = g_epoch[cta];

  if (threadIdx.x == 32) {
    asm volatile("prefetch.tensormap [%0];" ::"l"(&P.xA) : "memory");
    asm volatile("prefetch.tensormap [%0];" ::"l"(&P.wA) : "memory");
    asm volatile("prefetch.tensormap [%0];" ::"l"(&P.qkv) : "memory");
  }
  if (threadIdx.x == 0) {
    if (sb & 1023) __trap();
    const uint32_t bars = sb + OFF_BAR;
    for (int i = 0; i < (int)G_STAGES; i++) {
      mbar_init(bars + 8 * (B_GFULL + i), 1);
      mbar_init(bars + 8 * (B_GEMPTY + i), 2);
    }
    for (int i = 0; i < (int)A_STAGES; i++) {
      mbar_init(bars + 8 * (B_KFULL + i), 1);
      mbar_init(bars + 8 * (B_KEMPTY + i), 4);
      mbar_init(bars + 8 * (B_VFULL + i), 1);
      mbar_init(bars + 8 * (B_VEMPTY + i), 4);
    }
    mbar_init(bars + 8 * B_QFULL, 1);
    mbar_init(bars + 8 * B_QEMPTY, 8);
    mbar_init(bars + 8 * B_KVZ, 1);
    mbar_init(bars + 8 * B_KVLD, 1);
    mbar_init(bars + 8 * B_DONE, 3);
    for (int i = 0; i < 6; i++) mbar_init(bars + 8 * (B_GSIG + i), 4);
    for (int i = 0; i < 4; i++) mbar_init(bars + 8 * (B_ASIG + i), 8);
    asm volatile("fence.mbarrier_init.release.cluster;" ::: "memory");
  }
  asm volatile("st.shared.b32 [%0], %1;" ::"r"(sb + OFF_KVZ + threadIdx.x * 4), "r"(0x3F803F80u) : "memory");
  fence_proxy_async_smem();
  __syncthreads();
  cluster_sync();

  if (wgid == 0) {
    asm volatile("setmaxnreg.dec.sync.aligned.u32 24;");
    const int warp = threadIdx.x >> 5, lane = threadIdx.x & 31;
    if (warp == 0) {
      if (lane == 0) gemm_producer(P, sb, pair, rank, epoch);
    } else if (warp == 1) {
      if (lane == 0) attn_producer(P, sb, pair, rank, epoch);
    } else if (warp == 2) {
      utility_gemm(sb, lane, pair, epoch);
    } else {
      utility_attn(sb, lane, cta, epoch);
    }
    __syncwarp();
    cluster_sync();
    if (threadIdx.x == 0) g_epoch[cta] = epoch + 1;
  } else if (wgid == 1) {
    asm volatile("setmaxnreg.inc.sync.aligned.u32 168;");
    gemm_consumer(P, sb, epoch);
    if ((threadIdx.x & 127) == 0) mbar_arrive(sb + OFF_BAR + 8 * B_DONE);
    __syncwarp();
    cluster_sync();
  } else {
    asm volatile("setmaxnreg.inc.sync.aligned.u32 160;");
    attn_consumer(sb);
    if ((threadIdx.x & 127) == 0) mbar_arrive(sb + OFF_BAR + 8 * B_DONE);
    __syncwarp();
    cluster_sync();
  }
}

typedef CUresult (*EncodeFn)(CUtensorMap*, CUtensorMapDataType, cuuint32_t, void*, const cuuint64_t*, const cuuint64_t*,
                             const cuuint32_t*, const cuuint32_t*, CUtensorMapInterleave, CUtensorMapSwizzle,
                             CUtensorMapL2promotion, CUtensorMapFloatOOBfill);

void make_map(EncodeFn enc, CUtensorMap* tm, const void* ptr, uint64_t rows, uint64_t cols, uint32_t box_rows,
              uint32_t box_cols, CUtensorMapSwizzle swz) {
  cuuint64_t gd[2] = {cols, rows};
  cuuint64_t gs[1] = {cols * 2};
  cuuint32_t bd[2] = {box_cols, box_rows};
  cuuint32_t es[2] = {1, 1};
  enc(tm, CU_TENSOR_MAP_DATA_TYPE_BFLOAT16, 2, const_cast<void*>(ptr), gd, gs, bd, es, CU_TENSOR_MAP_INTERLEAVE_NONE, swz,
      CU_TENSOR_MAP_L2_PROMOTION_L2_256B, CU_TENSOR_MAP_FLOAT_OOB_FILL_NONE);
}

}

extern "C" void kernel_launch(void* const* d_in, const int* in_sizes, int n_in, void* d_out, int out_size) {
  (void)in_sizes, (void)n_in, (void)out_size;
  static EncodeFn enc = nullptr;
  static void *p_qkv, *p_oA, *p_oB;
  if (!enc) {
    void* fn = nullptr;
    cudaDriverEntryPointQueryResult qr;
    cudaGetDriverEntryPoint("cuTensorMapEncodeTiled", &fn, cudaEnableDefault, &qr);
    enc = (EncodeFn)fn;
    cudaGetSymbolAddress(&p_qkv, g_qkvA);
    cudaGetSymbolAddress(&p_oA, g_oA);
    cudaGetSymbolAddress(&p_oB, g_oB);
    cudaFuncSetAttribute(fused_kernel, cudaFuncAttributeMaxDynamicSharedMemorySize, SMEM_BYTES);
  }
  Params P;
  make_map(enc, &P.xA, d_in[0], SEQ, DM, 128, 64, CU_TENSOR_MAP_SWIZZLE_128B);
  make_map(enc, &P.wA, d_in[1], DM, 3 * DM, 64, 64, CU_TENSOR_MAP_SWIZZLE_128B);
  make_map(enc, &P.woA, d_in[2], DM, DM, 64, 64, CU_TENSOR_MAP_SWIZZLE_128B);
  make_map(enc, &P.xB, d_in[3], SEQ, DM, 128, 64, CU_TENSOR_MAP_SWIZZLE_128B);
  make_map(enc, &P.wB, d_in[4], DM, 3 * DM, 64, 64, CU_TENSOR_MAP_SWIZZLE_128B);
  make_map(enc, &P.woB, d_in[5], DM, DM, 64, 64, CU_TENSOR_MAP_SWIZZLE_128B);
  make_map(enc, &P.oA, p_oA, SEQ, DM, 128, 64, CU_TENSOR_MAP_SWIZZLE_128B);
  make_map(enc, &P.oB, p_oB, SEQ, DM, 128, 64, CU_TENSOR_MAP_SWIZZLE_128B);
  make_map(enc, &P.qkv, p_qkv, 3 * 32 * SEQ, 32, 128, 32, CU_TENSOR_MAP_SWIZZLE_64B);
  make_map(enc, &P.out, d_out, SEQ, 2 * DM, 64, 64, CU_TENSOR_MAP_SWIZZLE_128B);
  fused_kernel<<<128, 512, SMEM_BYTES, cudaStreamPerThread>>>(P);
}
```
